```python
import torch

def _softmax(x, axis=-1):
    return torch.softmax(x, dim=axis)
def _gelu(x):
    return torch.nn.functional.gelu(x, approximate="tanh")
def _silu(x):
    return torch.nn.functional.silu(x)
def _sigmoid(x):
    return torch.sigmoid(x)
def _layernorm(x, axis=-1, eps=1e-5):
    m = x.mean(dim=axis, keepdim=True)
    v = x.var(dim=axis, keepdim=True, unbiased=False)
    return (x - m) / torch.sqrt(v + eps)
def _scatter_add(tgt, idx, src, axis=0):
    return tgt.clone().index_add_(axis, idx, src)
def _segment_sum(src, seg, n):
    out = torch.zeros((n,) + src.shape[1:], dtype=src.dtype)
    return out.index_add_(0, seg, src)
def _pad(x, pw):
    flat = tuple(v for pair in reversed(pw) for v in pair)
    return torch.nn.functional.pad(x, flat)

kernel_name = 'standalone__instancenorm__prompt'

def setup_inputs():

    _w = (lambda a: (lambda t: t.to(torch.bfloat16) if t.is_floating_point() else t)(torch.as_tensor(a)))
    B, C, H, W = 1, 640, 2048, 32
    return {
        "x": _w(abs((lambda *s: torch.randn(*s, dtype=torch.bfloat16) * 0.05)(B, C, H, W))),
        "g": _w((lambda *s: torch.randn(*s, dtype=torch.bfloat16) * 0.05)(C) + 1.0),
        "b": _w((lambda *s: torch.randn(*s, dtype=torch.bfloat16) * 0.4)(C)),
    }

def reference(x, g, b):
    mu = x.mean(axis=(-2, -1), keepdims=True)
    var = ((x - mu) ** 2).mean(axis=(-2, -1), keepdims=True)
    xhat = (x - mu) / torch.sqrt(var + 1e-5)
    return xhat * g.reshape(1, -1, 1, 1) + b.reshape(1, -1, 1, 1)
```

```cpp
#include <cuda_runtime.h>
#include <cuda_bf16.h>
#include <stdint.h>

namespace {

constexpr int CH = 8192;
constexpr int CPC = 16;
constexpr int NCH = 5;
constexpr int NK = CPC * NCH;
constexpr int NSM = 28;
constexpr int NR = 26;
constexpr int NS = 6;
constexpr int GRID = 128;
constexpr int H1 = 16 + NR;
constexpr int HC4 = 16;
constexpr int PACE16 = 48;
constexpr int SLACK = 1;
constexpr int OFF_FULL = NSM * CH;
constexpr int OFF_EMPTY = OFF_FULL + NK * 8;
constexpr int OFF_STAT = OFF_EMPTY + NK * 8;
constexpr int OFF_PART = OFF_STAT + 64;
constexpr int OFF_GB = OFF_PART + NCH * 8 * 8;
constexpr int SMEM = OFF_GB + NCH * 8;
constexpr size_t CBYTES = (size_t)CPC * CH;
constexpr size_t CSTRIDE = GRID * CBYTES;

__device__ __forceinline__ uint32_t smem_u32(const void* p) { return (uint32_t)__cvta_generic_to_shared(p); }
__device__ __forceinline__ void mbar_init(uint32_t bar, uint32_t cnt) {
    asm volatile("mbarrier.init.shared::cta.b64 [%0], %1;" ::"r"(bar), "r"(cnt) : "memory");
}
__device__ __forceinline__ void mbar_expect_tx(uint32_t bar, uint32_t bytes) {
    asm volatile("mbarrier.arrive.expect_tx.shared::cta.b64 _, [%0], %1;" ::"r"(bar), "r"(bytes) : "memory");
}
__device__ __forceinline__ void mbar_arrive(uint32_t bar, uint32_t n) {
    asm volatile("mbarrier.arrive.shared::cta.b64 _, [%0], %1;" ::"r"(bar), "r"(n) : "memory");
}
__device__ __forceinline__ void mbar_wait(uint32_t bar) {
#pragma unroll 1
    for (int it = 0; it < (1 << 22); it++) {
        uint32_t ok;
        asm volatile("{\n.reg .pred p;\nmbarrier.try_wait.parity.shared::cta.b64 p, [%1], 0;\nselp.u32 %0, 1, 0, p;\n}"
                     : "=r"(ok) : "r"(bar) : "memory");
        if (ok) return;
    }
    __trap();
}
__device__ __forceinline__ void tma_load(uint32_t dst, const void* src, uint32_t bar, uint64_t pol) {
    asm volatile("cp.async.bulk.shared::cluster.global.mbarrier::complete_tx::bytes.L2::cache_hint [%0], [%1], %2, [%3], %4;"
                 ::"r"(dst), "l"(src), "r"(CH), "r"(bar), "l"(pol) : "memory");
}
__device__ __forceinline__ void fence_async() { asm volatile("fence.proxy.async.shared::cta;" ::: "memory"); }
__device__ __forceinline__ uint4 lds128(uint32_t a) {
    uint4 v;
    asm volatile("ld.shared.v4.u32 {%0,%1,%2,%3}, [%4];" : "=r"(v.x), "=r"(v.y), "=r"(v.z), "=r"(v.w) : "r"(a) : "memory");
    return v;
}
__device__ __forceinline__ void stg128(void* p, uint4 v) {
    asm volatile("st.global.v4.u32 [%0], {%1,%2,%3,%4};" ::"l"(p), "r"(v.x), "r"(v.y), "r"(v.z), "r"(v.w) : "memory");
}
__device__ __forceinline__ float blo(uint32_t u) { return __uint_as_float(u << 16); }
__device__ __forceinline__ float bhi(uint32_t u) { return __uint_as_float(u & 0xffff0000u); }
__device__ __forceinline__ uint32_t norm2(uint32_t u, float mean, float sc, float be) {
    float lo = fmaf(blo(u) - mean, sc, be), hi = fmaf(bhi(u) - mean, sc, be);
    uint32_t r;
    asm("cvt.rn.bf16x2.f32 %0, %1, %2;" : "=r"(r) : "f"(hi), "f"(lo));
    return r;
}
__device__ __forceinline__ uint4 norm8(uint4 v, float mean, float sc, float be) {
    return make_uint4(norm2(v.x, mean, sc, be), norm2(v.y, mean, sc, be), norm2(v.z, mean, sc, be), norm2(v.w, mean, sc, be));
}
__device__ __forceinline__ void opaque(uint4& v) { asm volatile("" : "+r"(v.x), "+r"(v.y), "+r"(v.z), "+r"(v.w)); }

__host__ __device__ constexpr int slot_of(int k) {
    if (k >= H1 + NSM) k -= NSM;
    return k < 16 ? k : (k < H1 + 12 ? 16 + (k - 16) % 12 : k - (H1 + 12));
}
__host__ __device__ constexpr int prev_of(int k) {
    return k < NSM ? -1 : (k < H1 + 12 ? k - 12 : (k < H1 + NSM ? k - (H1 + 12) : k - NSM));
}

__device__ __forceinline__ float wsum(float v) {
#pragma unroll
    for (int o = 1; o < 32; o <<= 1) v += __shfl_xor_sync(0xffffffffu, v, o);
    return v;
}
struct Stat { float a1, b1, a2, b2, K; };
__device__ __forceinline__ void stat_begin(Stat& s, uint4 v) {
    float m = ((blo(v.x) + bhi(v.x)) + (blo(v.y) + bhi(v.y))) + ((blo(v.z) + bhi(v.z)) + (blo(v.w) + bhi(v.w)));
    s.K = wsum(m) * (1.0f / 256.0f);
    s.a1 = s.b1 = s.a2 = s.b2 = 0.f;
}
__device__ __forceinline__ void stat_add2(Stat& s, uint32_t u) {
    float lo = blo(u) - s.K, hi = bhi(u) - s.K;
    s.a1 += lo; s.b1 += hi; s.a2 = fmaf(lo, lo, s.a2); s.b2 = fmaf(hi, hi, s.b2);
}
__device__ __forceinline__ void stat_add(Stat& s, uint4 v) { stat_add2(s, v.x); stat_add2(s, v.y); stat_add2(s, v.z); stat_add2(s, v.w); }
__device__ __forceinline__ void stat_end(Stat& s, uint32_t sb, int c, int warp, int lane) {
    float s1 = wsum(s.a1 + s.b1), s2 = wsum(s.a2 + s.b2);
    if (lane == 0) {
        float md = s1 * (1.0f / 8192.0f);
        float mean = s.K + md;
        float m2 = fmaf(-s1, md, s2);
        asm volatile("st.shared.v2.f32 [%0], {%1,%2};" ::"r"(sb + OFF_PART + (c * 8 + warp) * 8), "f"(mean), "f"(m2) : "memory");
        mbar_arrive(sb + OFF_STAT + c * 8, 1);
    }
}
__device__ __forceinline__ void finalize(uint32_t sb, int c, int lane, float& mean, float& sc, float& be) {
    mbar_wait(sb + OFF_STAT + c * 8);
    float mw, m2, ga;
    asm volatile("ld.shared.v2.f32 {%0,%1}, [%2];" : "=f"(mw), "=f"(m2) : "r"(sb + OFF_PART + (c * 8 + (lane & 7)) * 8) : "memory");
    asm volatile("ld.shared.v2.f32 {%0,%1}, [%2];" : "=f"(ga), "=f"(be) : "r"(sb + OFF_GB + c * 8) : "memory");
    float m = mw;
    m += __shfl_xor_sync(0xffffffffu, m, 1); m += __shfl_xor_sync(0xffffffffu, m, 2); m += __shfl_xor_sync(0xffffffffu, m, 4);
    m *= 0.125f;
    float d = mw - m;
    m2 = fmaf(d * 8192.0f, d, m2);
    m2 += __shfl_xor_sync(0xffffffffu, m2, 1); m2 += __shfl_xor_sync(0xffffffffu, m2, 2); m2 += __shfl_xor_sync(0xffffffffu, m2, 4);
    float var = m2 * (1.0f / 65536.0f);
    var = var < 0.f ? 0.f : var;
    mean = m;
    sc = ga * rsqrtf(var + 1e-5f);
}

__global__ void __launch_bounds__(384, 1)
instancenorm_kernel(const __nv_bfloat16* __restrict__ x, const __nv_bfloat16* __restrict__ gam,
                    const __nv_bfloat16* __restrict__ bet, __nv_bfloat16* __restrict__ out) {
    extern __shared__ __align__(1024) char smem[];
    const uint32_t sb = smem_u32(smem);
    const int tid = threadIdx.x, warp = tid >> 5, lane = tid & 31;
    const int c0 = blockIdx.x;
    const char* xin = (const char*)x + (size_t)c0 * CBYTES;
    char* yout = (char*)out + (size_t)c0 * CBYTES;

    uint64_t pol = 0;
    if (lane == 0) {
        if (warp == 8) {
#pragma unroll
            for (int k = 0; k < 10; k++) mbar_init(sb + OFF_FULL + 8 * k, 1);
            fence_async();
            asm volatile("createpolicy.fractional.L2::evict_first.b64 %0, 1.0;" : "=l"(pol));
#pragma unroll
            for (int k = 0; k < NS; k++) {
                mbar_expect_tx(sb + OFF_FULL + 8 * k, CH);
                tma_load(sb + k * CH, xin + k * CH, sb + OFF_FULL + 8 * k, pol);
            }
        } else if (warp < 8) {
            const uint32_t ub = sb + __shfl_sync(1u, warp, 0) * 80;
            if (warp > 0) {
#pragma unroll
                for (int i = 0; i < 10; i++) mbar_init(ub + OFF_FULL + 8 * i, 1);
            }
#pragma unroll
            for (int i = 0; i < 10; i++) mbar_init(ub + OFF_EMPTY + 8 * i, 24);
            fence_async();
        } else if (warp == 9) {
#pragma unroll
            for (int i = 0; i < NCH; i++) mbar_init(sb + OFF_STAT + 8 * i, 9);
        }
    }
    __syncthreads();

    if (warp >= 8) {
        asm volatile("setmaxnreg.dec.sync.aligned.u32 40;");
        if (warp == 8) {
            if (lane == 0) {
                for (int k = NS; k < NK; k++) {
                    mbar_wait(sb + OFF_FULL + 8 * (k - NS));
                    int p = prev_of(k);
                    if (p >= 0) mbar_wait(sb + OFF_EMPTY + 8 * p);
                    mbar_expect_tx(sb + OFF_FULL + 8 * k, CH);
                    tma_load(sb + slot_of(k) * CH, xin + (size_t)(k >> 4) * CSTRIDE + (k & 15) * CH, sb + OFF_FULL + 8 * k, pol);
                }
            }
        } else {
            if (warp == 9 && lane < NCH) {
                int c = c0 + lane * GRID;
                float ga = __bfloat162float(gam[c]), be = __bfloat162float(bet[c]);
                asm volatile("st.shared.v2.f32 [%0], {%1,%2};" ::"r"(sb + OFF_GB + lane * 8), "f"(ga), "f"(be) : "memory");
                mbar_arrive(sb + OFF_STAT + lane * 8, 1);
            }
            __syncwarp();
            int cur = -1;
            float mean = 0.f, sc = 0.f, be = 0.f;
            const int w = warp - 9;
#pragma unroll 1
            for (int j = 0; j < NK - NR - HC4; j++) {
                int k = j < 16 ? j : j + NR;
                int f = min(min(15 + ((j * PACE16) >> 4), j + (NSM + NR - NS) - SLACK), NK - 1);
                int c = k >> 4;
                uint32_t sa = sb + slot_of(k) * CH + lane * 16 + w * 2560;
                char* gp = yout + (size_t)c * CSTRIDE + (k & 15) * CH + lane * 16 + w * 2560;
                mbar_wait(sb + OFF_FULL + 8 * f);
                if (c != cur) { finalize(sb, c, lane, mean, sc, be); cur = c; }
                uint4 v0 = lds128(sa), v1 = lds128(sa + 512), v2 = lds128(sa + 1024);
                stg128(gp, norm8(v0, mean, sc, be));
                v0 = lds128(sa + 1536);
                stg128(gp + 512, norm8(v1, mean, sc, be));
                v1 = lds128(sa + 2048);
                stg128(gp + 1024, norm8(v2, mean, sc, be));
                if (w == 2) v2 = lds128(sa + 2560);
                __syncwarp();
                if (lane == 0) mbar_arrive(sb + OFF_EMPTY + 8 * k, 8);
                stg128(gp + 1536, norm8(v0, mean, sc, be));
                stg128(gp + 2048, norm8(v1, mean, sc, be));
                if (w == 2) stg128(gp + 2560, norm8(v2, mean, sc, be));
            }
        }
    } else {
        asm volatile("setmaxnreg.inc.sync.aligned.u32 232;");
        Stat st;
        uint4 r[NR][2];
        const uint32_t ta = sb + tid * 16;
#pragma unroll 1
        for (int k = 0; k < 16; k++) {
            mbar_wait(sb + OFF_FULL + 8 * k);
            uint4 v0 = lds128(ta + k * CH), v1 = lds128(ta + k * CH + 4096);
            if (k == 0) stat_begin(st, v0);
            stat_add(st, v0); stat_add(st, v1);
        }
        stat_end(st, sb, 0, warp, lane);
#pragma unroll
        for (int k = 16; k < H1; k++) {
            mbar_wait(sb + OFF_FULL + 8 * k);
            r[k - 16][0] = lds128(ta + slot_of(k) * CH);
            r[k - 16][1] = lds128(ta + slot_of(k) * CH + 4096);
            __syncwarp();
            if (lane == 0) mbar_arrive(sb + OFF_EMPTY + 8 * k, 3);
            if ((k & 15) == 0) stat_begin(st, r[k - 16][0]);
            stat_add(st, r[k - 16][0]); stat_add(st, r[k - 16][1]);
            if ((k & 15) == 15) stat_end(st, sb, k >> 4, warp, lane);
        }
#pragma unroll 1
        for (int k = H1; k < NK; k++) {
            uint32_t a = ta + slot_of(k) * CH;
            mbar_wait(sb + OFF_FULL + 8 * k);
            uint4 v0 = lds128(a), v1 = lds128(a + 4096);
            if ((k & 15) == 0) stat_begin(st, v0);
            stat_add(st, v0);
            stat_add(st, v1);
            if ((k & 15) == 15) stat_end(st, sb, k >> 4, warp, lane);
        }
        float mean, sc, be;
        char* const gp = yout + tid * 16;
#pragma unroll 2
        for (int k = NK - HC4; k < NK; k++) {
            if ((k & 15) == 0 || k == NK - HC4) finalize(sb, k >> 4, lane, mean, sc, be);
            uint32_t a = ta + slot_of(k) * CH;
            uint4 v0 = lds128(a), v1 = lds128(a + 4096);
            char* p = gp + (size_t)(k >> 4) * CSTRIDE + (k & 15) * CH;
            stg128(p, norm8(v0, mean, sc, be));
            stg128(p + 4096, norm8(v1, mean, sc, be));
        }
#pragma unroll
        for (int k = 16; k < H1; k++) {
            if ((k & 15) == 0) finalize(sb, k >> 4, lane, mean, sc, be);
            char* p = gp + (size_t)(k >> 4) * CSTRIDE + (k & 15) * CH;
            opaque(r[k - 16][0]); opaque(r[k - 16][1]);
            stg128(p, norm8(r[k - 16][0], mean, sc, be));
            stg128(p + 4096, norm8(r[k - 16][1], mean, sc, be));
        }
    }
}

}

extern "C" void kernel_launch(void* const* d_in, const int* in_sizes, int n_in, void* d_out, int out_size) {
    const __nv_bfloat16* x = (const __nv_bfloat16*)d_in[0];
    const __nv_bfloat16* g = (const __nv_bfloat16*)d_in[1];
    const __nv_bfloat16* b = (const __nv_bfloat16*)d_in[2];
    cudaFuncSetAttribute(instancenorm_kernel, cudaFuncAttributeMaxDynamicSharedMemorySize, SMEM);
    instancenorm_kernel<<<GRID, 384, SMEM>>>(x, g, b, (__nv_bfloat16*)d_out);
}
```

```cpp
#include <cuda_runtime.h>
#include <cuda_bf16.h>
#include <stdint.h>

namespace {

constexpr int CH = 8192;
constexpr int GRID = 128;
constexpr int NPC = 40;
constexpr int NK = 2 * NPC;
constexpr int NSM = 28;
constexpr int NR = 27;
constexpr int H1 = 16 + NR;
constexpr int NS = 5;
constexpr int TAU = 316;
constexpr int T0 = -1130;
constexpr int JW = 33;
constexpr int L0 = 9;
constexpr int PACE16 = 50;
constexpr int LMAX = NSM + NR - NS - 2;
constexpr int NFIN = NK - JW;
constexpr int DELTA8 = 25;
constexpr int GX = 7;
static_assert(JW >= NSM, "the drained smem chunks lie in the wrapped part of the ring");

constexpr int OFF_FULL = NSM * CH;
constexpr int OFF_EMPTY = OFF_FULL + NK * 8;
constexpr int OFF_STAT = OFF_EMPTY + NK * 8;
constexpr int OFF_FINB = OFF_STAT + NPC * 8;
constexpr int OFF_PART = OFF_FINB + NPC * 8;
constexpr int OFF_FIN = OFF_PART + 4 * 8 * 16;
constexpr int OFF_GB = OFF_FIN + NPC * 8;
constexpr int OFF_GOV = OFF_GB + NPC * 4;
constexpr int SMEM = OFF_GOV + 16;
static_assert(SMEM <= 232448, "smem");

__device__ unsigned int g_prog;
__device__ unsigned int g_tag[16 * 32];
__device__ __align__(256) uint4 g_mom[NPC * GRID * 2];

__device__ __forceinline__ uint32_t smem_u32(const void* p) { return (uint32_t)__cvta_generic_to_shared(p); }
__device__ __forceinline__ void mbar_init(uint32_t bar, uint32_t cnt) {
    asm volatile("mbarrier.init.shared::cta.b64 [%0], %1;" ::"r"(bar), "r"(cnt) : "memory");
}
__device__ __forceinline__ void mbar_expect_tx(uint32_t bar, uint32_t bytes) {
    asm volatile("mbarrier.arrive.expect_tx.shared::cta.b64 _, [%0], %1;" ::"r"(bar), "r"(bytes) : "memory");
}
__device__ __forceinline__ void mbar_arrive(uint32_t bar) {
    asm volatile("mbarrier.arrive.shared::cta.b64 _, [%0];" ::"r"(bar) : "memory");
}
__device__ __forceinline__ void mbar_arrive_n(uint32_t bar, uint32_t n) {
    asm volatile("mbarrier.arrive.shared::cta.b64 _, [%0], %1;" ::"r"(bar), "r"(n) : "memory");
}
__device__ __forceinline__ void mbar_wait(uint32_t bar) {
#pragma unroll 1
    for (int it = 0; it < (1 << 22); it++) {
        uint32_t ok;
        asm volatile("{\n.reg .pred p;\nmbarrier.try_wait.parity.shared::cta.b64 p, [%1], 0;\nselp.u32 %0, 1, 0, p;\n}"
                     : "=r"(ok) : "r"(bar) : "memory");
        if (ok) return;
    }
    __trap();
}
__device__ __forceinline__ int mbar_try(uint32_t bar, uint32_t ns) {
    uint32_t ok;
    asm volatile("{\n.reg .pred p;\nmbarrier.try_wait.parity.shared::cta.b64 p, [%1], 0, %2;\nselp.u32 %0, 1, 0, p;\n}"
                 : "=r"(ok) : "r"(bar), "r"(ns) : "memory");
    return ok;
}
__device__ __forceinline__ void tma_load(uint32_t dst, const void* src, uint32_t bar, uint64_t pol) {
    asm volatile("cp.async.bulk.shared::cluster.global.mbarrier::complete_tx::bytes.L2::cache_hint [%0], [%1], %2, [%3], %4;"
                 ::"r"(dst), "l"(src), "r"(CH), "r"(bar), "l"(pol) : "memory");
}
__device__ __forceinline__ uint4 lds128(uint32_t a) {
    uint4 v;
    asm volatile("ld.shared.v4.u32 {%0,%1,%2,%3}, [%4];" : "=r"(v.x), "=r"(v.y), "=r"(v.z), "=r"(v.w) : "r"(a) : "memory");
    return v;
}
__device__ __forceinline__ void lds64f(uint32_t a, float& x, float& y) {
    asm volatile("ld.shared.v2.f32 {%0,%1}, [%2];" : "=f"(x), "=f"(y) : "r"(a) : "memory");
}
__device__ __forceinline__ void sts64f(uint32_t a, float x, float y) {
    asm volatile("st.shared.v2.f32 [%0], {%1,%2};" ::"r"(a), "f"(x), "f"(y) : "memory");
}
__device__ __forceinline__ int ldsv(uint32_t a) {
    int v;
    asm volatile("ld.volatile.shared.u32 %0, [%1];" : "=r"(v) : "r"(a) : "memory");
    return v;
}
__device__ __forceinline__ void stsv(uint32_t a, int v) { asm volatile("st.volatile.shared.u32 [%0], %1;" ::"r"(a), "r"(v) : "memory"); }
__device__ __forceinline__ void wait_gt(uint32_t a, int v) {
#pragma unroll 1
    for (int it = 0; it < (1 << 26); it++) if (ldsv(a) > v) return;
    __trap();
}
__device__ __forceinline__ void stg128(void* p, uint4 v) {
    asm volatile("st.global.L1::no_allocate.v4.u32 [%0], {%1,%2,%3,%4};" ::"l"(p), "r"(v.x), "r"(v.y), "r"(v.z), "r"(v.w) : "memory");
}
__device__ __forceinline__ uint32_t now_ns() { uint32_t t; asm volatile("mov.u32 %0, %globaltimer_lo;" : "=r"(t)); return t; }
__device__ __forceinline__ int laneid() { int l; asm volatile("mov.u32 %0, %laneid;" : "=r"(l)); return l; }
__device__ __forceinline__ float blo(uint32_t u) { return __uint_as_float(u << 16); }
__device__ __forceinline__ float bhi(uint32_t u) { return __uint_as_float(u & 0xffff0000u); }
__device__ __forceinline__ uint32_t norm2(uint32_t u, float sc, float sh) {
    float lo = fmaf(blo(u), sc, sh), hi = fmaf(bhi(u), sc, sh);
    uint32_t r;
    asm("cvt.rn.bf16x2.f32 %0, %1, %2;" : "=r"(r) : "f"(hi), "f"(lo));
    return r;
}
__device__ __forceinline__ uint4 norm8(uint4 v, float sc, float sh) {
    return make_uint4(norm2(v.x, sc, sh), norm2(v.y, sc, sh), norm2(v.z, sc, sh), norm2(v.w, sc, sh));
}
__device__ __forceinline__ void opaque(uint4& v) { asm volatile("" : "+r"(v.x), "+r"(v.y), "+r"(v.z), "+r"(v.w)); }
template <int I> struct IC { static constexpr int value = I; };
template <int B, int E, class F> __device__ __forceinline__ void static_for(F&& f) {
    if constexpr (B < E) { f(IC<B>{}); static_for<B + 1, E>(f); }
}

__host__ __device__ constexpr int slot_of(int k) {
    return k < 16 ? k : (k < H1 ? 16 + (k + 120 - H1) % 12 : (k - H1 + 16) % NSM);
}
struct Rounds { int of[NPC]; };
constexpr Rounds ROUNDS = {{0, 1, 2, 3, 22, 23, 24, 26, 36, 11, 21, 12, 20, 19, 18, 17, 16, 15, 14, 13,
                            37, 27, 25, 28, 31, 30, 4, 29, 33, 34, 10, 9, 32, 8, 5, 7, 38, 39, 35, 6}};
constexpr bool is_permutation(const Rounds& r) {
    unsigned long long seen = 0;
    for (int i = 0; i < NPC; i++) seen |= 1ull << r.of[i];
    return seen == (1ull << NPC) - 1;
}
static_assert(is_permutation(ROUNDS), "rounds");

struct Stat { float a1, a2, b2; };
__device__ __forceinline__ void stat_add2(Stat& s, uint32_t u) {
    const float lo = blo(u), hi = bhi(u);
    s.a1 += lo + hi; s.a2 = fmaf(lo, lo, s.a2); s.b2 = fmaf(hi, hi, s.b2);
}
__device__ __forceinline__ void stat_add(Stat& s, uint4 v) { stat_add2(s, v.x); stat_add2(s, v.y); stat_add2(s, v.z); stat_add2(s, v.w); }
__device__ __forceinline__ float sum8(float v) {
    v += __shfl_xor_sync(0xffffffffu, v, 1); v += __shfl_xor_sync(0xffffffffu, v, 2); v += __shfl_xor_sync(0xffffffffu, v, 4);
    return v;
}

__global__ void __launch_bounds__(384, 1)
instancenorm_kernel(const __nv_bfloat16* __restrict__ x, const __nv_bfloat16* __restrict__ gam,
                    const __nv_bfloat16* __restrict__ bet, __nv_bfloat16* __restrict__ out,
                    const __grid_constant__ Rounds rounds) {
    extern __shared__ __align__(1024) char smem[];
    const uint32_t sb = smem_u32(smem);
    const int tid = threadIdx.x, warp = tid >> 5, lane = tid & 31;
    const int bid = blockIdx.x;
    auto goff = [&](int k) { return (uint32_t)rounds.of[k >> 1] * (GRID * 2 * CH) + (k & 1) * CH; };
    const char* xin = (const char*)x + (size_t)bid * (2 * CH);
    char* yout = (char*)out + (size_t)bid * (2 * CH);

    uint64_t pol;
    asm volatile("createpolicy.fractional.L2::evict_first.b64 %0, 1.0;" : "=l"(pol));
    if (tid == 0)
        asm volatile("cp.async.bulk.prefetch.L2.global.L2::cache_hint [%0], %1, %2;" ::"l"(xin + goff(0)), "r"(2 * CH), "l"(pol) : "memory");
    uint32_t tn = 0;
    if (lane == 0) {
        if (warp == 8) {
#pragma unroll
            for (int k = 0; k < NS; k++) {
                mbar_init(sb + OFF_FULL + 8 * k, 1);
                mbar_expect_tx(sb + OFF_FULL + 8 * k, CH);
                tma_load(sb + k * CH, xin + goff(k), sb + OFF_FULL + 8 * k, pol);
            }
#pragma unroll
            for (int k = NS; k < 10; k++) mbar_init(sb + OFF_FULL + 8 * k, 1);
            tn = now_ns() + (uint32_t)(T0 + NS * TAU);
        } else if (warp < 8) {
            const uint32_t uw = __shfl_sync(1u, warp, 0);
            if (warp > 0) {
#pragma unroll
                for (int i = 0; i < 10; i++) mbar_init(sb + uw * 80 + OFF_FULL + 8 * i, 1);
            }
#pragma unroll
            for (int i = 0; i < 10; i++) mbar_init(sb + uw * 80 + OFF_EMPTY + 8 * i, 8);
#pragma unroll
            for (int i = 0; i < 5; i++) { mbar_init(sb + uw * 40 + OFF_STAT + 8 * i, 17); mbar_init(sb + uw * 40 + OFF_FINB + 8 * i, 1); }
        } else if (warp == 9) {
            stsv(sb + OFF_GOV, 0);
            stsv(sb + OFF_GOV + 4, DELTA8 >> 3);
            stsv(sb + OFF_GOV + 8, 0);
            if (bid == 0) g_prog = 0;
        }
    }
    __syncthreads();

    if (warp >= 8) {
        asm volatile("setmaxnreg.dec.sync.aligned.u32 24;");
        if (warp == 8) {
            if (lane == 0) {
                int s = NS;
#pragma unroll 1
                for (int k = NS; k < NK; k++) {
                    if (k == 16) s = slot_of(16);
                    const int p = k < H1 + 12 ? k - 12 : (k < H1 + NSM ? k - (H1 + 12) : k - NSM);
                    const int lag = (int)(now_ns() - tn);
                    tn += TAU;
                    const int ns = k < 10 ? NS : NS + (lag > 128) - (lag < -128);
                    mbar_wait(sb + OFF_FULL + 8 * (k - ns));
                    if (k >= NSM) mbar_wait(sb + OFF_EMPTY + 8 * p);
                    mbar_expect_tx(sb + OFF_FULL + 8 * k, CH);
                    tma_load(sb + s * CH, xin + goff(k), sb + OFF_FULL + 8 * k, pol);
                    if (++s == NSM) s = k < H1 ? 16 : 0;
                }
                int rep = 0;
#pragma unroll 1
                for (int it = 0; it < 160; it++) {
                    const int own = ldsv(sb + OFF_GOV);
                    if (own >= NFIN - GX) break;
                    unsigned tot;
                    asm volatile("atom.relaxed.gpu.global.add.u32 %0, [%1], %2;" : "=r"(tot) : "l"(&g_prog), "r"(own - rep) : "memory");
                    rep = own;
                    stsv(sb + OFF_GOV + 4, (tot + DELTA8 * (GRID / 8)) / GRID);
                }
                stsv(sb + OFF_GOV + 4, NK);
                asm volatile("red.relaxed.gpu.global.add.u32 [%0], %1;" ::"l"(&g_prog), "r"(NFIN - rep) : "memory");
            }
        } else if (warp == 9) {
            const int grp = bid >> 3, h = lane >> 3;
            uint32_t tag;
            asm volatile("ld.relaxed.gpu.global.u32 %0, [%1];" : "=r"(tag) : "l"(&g_tag[grp * 32]) : "memory");
            tag += 1;
            int p = 0, q = 0;
#pragma unroll 1
            for (int it = 0; q < NPC; it++) {
                if (it == (1 << 22)) asm volatile("trap;");
                uint64_t u0 = 0, u1 = 0;
                if (q + h < NPC && q + h + min(1 + q + h, 3) < p)
                    asm volatile("ld.relaxed.gpu.global.v2.b64 {%0,%1}, [%2];" : "=l"(u0), "=l"(u1)
                                 : "l"(g_mom + ((q + h) * GRID + grp * 8 + (lane & 7)) * 2) : "memory");
#pragma unroll 1
                for (int i = 0; i < 2; i++, p++) {
                    if (p >= NPC) { __nanosleep(300); continue; }
                    if (!__all_sync(0xffffffffu, mbar_try(sb + OFF_STAT + 8 * p, 2000))) break;
                    const uint4 t = lds128(sb + OFF_PART + ((p & 3) * 8 + (lane & 7)) * 16);
                    const float s1 = __uint_as_float(t.x);
                    const float mw = fmaf(s1, 1.0f / 32.0f, __uint_as_float(t.y));
                    const float m = sum8(mw) * 0.125f, d = mw - m;
                    const float m2 = sum8(fmaf(d * 1024.0f, d, fmaf(-s1, s1, __uint_as_float(t.z))));
                    if (lane < 2) {
                        stsv(sb + OFF_GOV + 8, p + 1);
                        asm volatile("st.relaxed.gpu.global.v2.b64 [%0], {%1,%2};" ::"l"(g_mom + (p * GRID + bid) * 2 + lane),
                                     "l"((uint64_t)tag << 32 | __float_as_uint(m)), "l"((uint64_t)tag << 32 | __float_as_uint(m2)) : "memory");
                    }
                }
                const uint32_t ok = __ballot_sync(0xffffffffu, (uint32_t)(u0 >> 32) == tag && (uint32_t)(u1 >> 32) == tag);
                const int nq = __clz(__brev(~ok)) >> 3;
                if (nq) {
                    const float mw = __uint_as_float((uint32_t)u0);
                    const float m = sum8(mw) * 0.125f, d = mw - m;
                    const float var = sum8(fmaf(d * 8192.0f, d, __uint_as_float((uint32_t)u1))) * (1.0f / 65536.0f);
                    if (h < nq && (lane & 7) == 0) {
                        const uint32_t gb = ldsv(sb + OFF_GB + (q + h) * 4);
                        const float sc = var <= 0.f ? 0.f : blo(gb) * rsqrtf(var + 1e-5f);
                        sts64f(sb + OFF_FIN + (q + h) * 8, sc, fmaf(-m, sc, bhi(gb)));
                        mbar_arrive(sb + OFF_FINB + 8 * (q + h));
                    }
                    __syncwarp();
                }
                q += nq;
            }
            if (lane == 0 && (bid & 7) == 0) g_tag[grp * 32] = tag;
        } else {
            if (tid < 320 + NPC) {
                const int c = rounds.of[tid - 320] * 16 + (bid >> 3);
                stsv(sb + OFF_GB + (tid - 320) * 4, (uint32_t)__bfloat16_as_ushort(gam[c]) | ((uint32_t)__bfloat16_as_ushort(bet[c]) << 16));
                mbar_arrive(sb + OFF_STAT + 8 * (tid - 320));
            }
            __syncwarp();
            const uint32_t o = (warp - 10) * 4096 + lane * 16;
            uint32_t sa = sb + o;
            char* const gw = yout + o;
#pragma unroll 1
            for (int j = 0; j < JW; j++, sa += CH) {
                const int k = j < 16 ? j : j + NR;
                const int f = min(min(L0 + ((j * PACE16) >> 4), j + LMAX), NK - 1);
                char* gp = gw + goff(k);
                if (j == NSM) sa -= NSM * CH;
                float sc, sh;
                mbar_wait(sb + OFF_FINB + 8 * (k >> 1));
                lds64f(sb + OFF_FIN + (k >> 1) * 8, sc, sh);
                mbar_wait(sb + OFF_FULL + 8 * f);
#pragma unroll
                for (int i = 0; i < 8; i += 2) {
                    const uint4 v0 = lds128(sa + i * 512), v1 = lds128(sa + i * 512 + 512);
                    if (i == 6) { __syncwarp(); if (lane == 0) mbar_arrive_n(sb + OFF_EMPTY + 8 * k, 4); }
                    stg128(gp + i * 512, norm8(v0, sc, sh));
                    stg128(gp + i * 512 + 512, norm8(v1, sc, sh));
                }
            }
        }
    } else {
        asm volatile("setmaxnreg.inc.sync.aligned.u32 240;");
        Stat st = {0.f, 0.f, 0.f};
        uint4 r[NR][2];
        static_for<0, NR>([&](auto I) { r[I.value][0] = make_uint4(0, 0, 0, 0); r[I.value][1] = make_uint4(0, 0, 0, 0); });
        const uint32_t ta = sb + tid * 16;
        uint32_t a = ta;
#pragma unroll 1
        for (int k = 0; k < NK; k++) {
            mbar_wait(sb + OFF_FULL + 8 * k);
            const uint4 v0 = lds128(a), v1 = lds128(a + 4096);
            stat_add(st, v0); stat_add(st, v1);
            if (k & 1) {
                const int l = laneid();
                const float mt = st.a1 * (1.0f / 32.0f);
                const float K = __shfl_sync(0xffffffffu, mt, 0), d = mt - K;
                const float s2 = fmaf(d * 32.0f, d, fmaf(-st.a1, mt, st.a2 + st.b2));
                float s = (l & 16) ? s2 : d;
                s += __shfl_xor_sync(0xffffffffu, (l & 16) ? d : s2, 16);
                s += __shfl_xor_sync(0xffffffffu, s, 8);
                s = sum8(s);
                wait_gt(sb + OFF_GOV + 8, (k >> 1) - 4);
                if ((l & 15) == 0) {
                    sts64f(sb + OFF_PART + (k & 6) * 64 + ((ta - sb) >> 8) * 8, s, K);
                    mbar_arrive(sb + OFF_STAT + 8 * (k >> 1));
                }
                st.a1 = st.a2 = st.b2 = 0.f;
            }
            a += CH;
            if (a == ta + NSM * CH) a = k < H1 ? ta + 16 * CH : ta;
            if (k == 15) a = ta + slot_of(16) * CH;
            if ((k & 3) == 3 && k >= 16 && k < H1 + 3) {
                static_for<0, NR>([&](auto I) {
                    constexpr int i = I.value;
                    asm volatile("{\n.reg .pred p;\nsetp.eq.s32 p, %8, %9;\n"
                                 "@p ld.shared.v4.u32 {%0,%1,%2,%3}, [%10+%11];\n"
                                 "@p ld.shared.v4.u32 {%4,%5,%6,%7}, [%10+%12];\n}"
                                 : "+r"(r[i][0].x), "+r"(r[i][0].y), "+r"(r[i][0].z), "+r"(r[i][0].w),
                                   "+r"(r[i][1].x), "+r"(r[i][1].y), "+r"(r[i][1].z), "+r"(r[i][1].w)
                                 : "r"(k), "n"(19 + i / 4 * 4), "r"(ta), "n"(slot_of(16 + i) * CH), "n"(slot_of(16 + i) * CH + 4096)
                                 : "memory");
                });
                __syncwarp();
                const int l = laneid();
                if (l < 4 && k - l < H1) mbar_arrive(sb + OFF_EMPTY + 8 * (k - l));
            }
        }
        char* const gp = yout + tid * 16;
#pragma unroll 1
        for (int m = 0; m < NFIN; m++) {
            const int kk = m < NFIN - NR ? JW + NR + m : (m == NFIN - NR ? H1 - 1 : 15 + m - (NFIN - NR));
            if (tid == 0) stsv(sb + OFF_GOV, m);
            float sc, sh;
            uint4 v0, v1;
            if (kk >= H1) {
                const uint32_t sa = ta + (kk - NR - NSM) * CH;
                mbar_wait(sb + OFF_FINB + 8 * (kk >> 1));
                lds64f(sb + OFF_FIN + (kk >> 1) * 8, sc, sh);
                v0 = lds128(sa); v1 = lds128(sa + 4096);
            } else {
                lds64f(sb + OFF_FIN + (kk >> 1) * 8, sc, sh);
                switch (kk - 16) {
#define KC(i) case i: v0 = r[i][0]; v1 = r[i][1]; opaque(v0); opaque(v1); break;
                    KC(0) KC(1) KC(2) KC(3) KC(4) KC(5) KC(6) KC(7) KC(8) KC(9) KC(10) KC(11) KC(12)
                    KC(13) KC(14) KC(15) KC(16) KC(17) KC(18) KC(19) KC(20) KC(21) KC(22) KC(23) KC(24) KC(25)
                    default: v0 = r[NR - 1][0]; v1 = r[NR - 1][1]; opaque(v0); opaque(v1); break;
#undef KC
                }
            }
            v0 = norm8(v0, sc, sh);
            char* p = gp + goff(kk);
#pragma unroll 1
            for (int it = 0; it < (1 << 16) && m > ldsv(sb + OFF_GOV + 4); it++) {}
            opaque(v1);
            stg128(p, v0); stg128(p + 4096, norm8(v1, sc, sh));
        }
        static_assert(NR == 27, "switch above");
    }
}

}

extern "C" void kernel_launch(void* const* d_in, const int* in_sizes, int n_in, void* d_out, int out_size) {
    const __nv_bfloat16* x = (const __nv_bfloat16*)d_in[0];
    const __nv_bfloat16* g = (const __nv_bfloat16*)d_in[1];
    const __nv_bfloat16* b = (const __nv_bfloat16*)d_in[2];
    cudaFuncSetAttribute(instancenorm_kernel, cudaFuncAttributeMaxDynamicSharedMemorySize, SMEM);
    instancenorm_kernel<<<GRID, 384, SMEM>>>(x, g, b, (__nv_bfloat16*)d_out, ROUNDS);
}
```
